```python
import torch

def _softmax(x, axis=-1):
    return torch.softmax(x, dim=axis)
def _gelu(x):
    return torch.nn.functional.gelu(x, approximate="tanh")
def _silu(x):
    return torch.nn.functional.silu(x)
def _sigmoid(x):
    return torch.sigmoid(x)
def _layernorm(x, axis=-1, eps=1e-5):
    m = x.mean(dim=axis, keepdim=True)
    v = x.var(dim=axis, keepdim=True, unbiased=False)
    return (x - m) / torch.sqrt(v + eps)
def _scatter_add(tgt, idx, src, axis=0):
    return tgt.clone().index_add_(axis, idx, src)
def _segment_sum(src, seg, n):
    out = torch.zeros((n,) + src.shape[1:], dtype=src.dtype)
    return out.index_add_(0, seg, src)
def _pad(x, pw):
    flat = tuple(v for pair in reversed(pw) for v in pair)
    return torch.nn.functional.pad(x, flat)

kernel_name = 'standalone__gqa_block_cached__near_ridge'

def setup_inputs():

    _w = (lambda a: (lambda t: t.to(torch.bfloat16) if t.is_floating_point() else t)(torch.as_tensor(a)))
    B, Sq, D = 16, 192, 640
    Hq, Hkv, Sk, Dh = 32, 32, 512, 128
    assert Hq % Hkv == 0, (Hq, Hkv)
    return {
        "x": _w((lambda *s: torch.randn(*s, dtype=torch.bfloat16) * 0.8)(B, Sq, D)),
        "k_cache": _w((lambda *s: torch.randn(*s, dtype=torch.bfloat16) * 0.8)(B, Hkv, Sk, Dh)),
        "v_cache": _w((lambda *s: torch.randn(*s, dtype=torch.bfloat16) * 0.05)(B, Hkv, Sk, Dh)),
        "wq": _w((lambda *s: torch.randn(*s, dtype=torch.bfloat16) * 0.8)(D, Hq * Dh) * (D ** -0.5)),
        "wo": _w((lambda *s: torch.randn(*s, dtype=torch.bfloat16) * 0.05)(Hq * Dh, D) * ((Hq * Dh) ** -0.5)),
    }

def reference(x, k_cache, v_cache, wq, wo):
    B, Sq, D = x.shape
    Hq, Dh = 32, 128
    Hkv = k_cache.shape[1]
    rep = Hq // Hkv
    q = (lambda x, *d: x.permute(*d))((x @ wq).reshape(B, Sq, Hq, Dh), 0, 2, 1, 3)
    k = (lambda x, n, axis: torch.repeat_interleave(x, n, dim=axis))(k_cache, rep, axis=1)
    v = (lambda x, n, axis: torch.repeat_interleave(x, n, dim=axis))(v_cache, rep, axis=1)
    scores = torch.einsum("bhqd,bhkd->bhqk", q, k) * (Dh ** -0.5)
    p = _softmax(scores, axis=-1)
    o = torch.einsum("bhqk,bhkd->bhqd", p, v)
    return (lambda x, *d: x.permute(*d))(o, 0, 2, 1, 3).reshape(B, Sq, Hq * Dh) @ wo
```

```cpp
#include <cuda_runtime.h>
#include <cuda_bf16.h>
#include <cuda.h>
#include <stdint.h>

namespace {

constexpr int NBATCH = 16, SQ = 192, DM = 640, NH = 32, SK = 512, DH = 128;
constexpr int NCTA = 128;
constexpr int NTHREADS = 512;

constexpr uint32_t SZ_QP = 40960;
constexpr uint32_t SZ_KV = 16384;
constexpr uint32_t SZ_OP = 49152;
constexpr uint32_t OFF_QS = 2 * SZ_QP + 16384;
constexpr uint32_t OFF_KV = 3 * SZ_QP;
constexpr uint32_t NKV = 6;
constexpr uint32_t OFF_QP3 = OFF_KV + 3 * SZ_KV;
constexpr uint32_t OFF_BAR = OFF_KV + NKV * SZ_KV;
constexpr uint32_t SMEM_BYTES = OFF_BAR + 512 + 1024;
__host__ __device__ constexpr uint32_t tile_bar(uint32_t j) { return j < 11 ? j : j - 11; }
__host__ __device__ constexpr uint32_t tile_off(uint32_t j) {
  return j < 6 ? OFF_KV + j * SZ_KV : (j < 11 ? (j - 6) * SZ_KV : OFF_KV + (j - 11) * SZ_KV);
}
__host__ __device__ constexpr uint32_t tile_par(uint32_t j, uint32_t it) { return j >= 11 ? 1u : (j >= 5 ? (it & 1u) : 0u); }
#define KV_T 700
#define KV_OUT 3
#define KV_START 600
#define STAG_D 6000
#define NX 1
#define QRS 4
#define AT_UNROLL_N 7
constexpr int AT_UNROLL = AT_UNROLL_N;
#define SPIN_NS 100

struct alignas(64) Maps {
  CUtensorMap x, wq, k, v, o, wo[4];
};

__device__ __nv_bfloat16 g_o[(size_t)NBATCH * NH * 2 * SQ * 64];
__device__ float4 g_part[(size_t)(NCTA / 2) * 20 * 384];
__device__ unsigned int g_oflag[NBATCH * NH];
__device__ unsigned int g_xflag[(NCTA / 2) * 12];

#define PROF2(role, slot) do { } while (0)
#define PROF(role, slot) do { } while (0)
#define TRACE(kind, st) do { } while (0)
__device__ __forceinline__ uint32_t smem_u32(const void* p) { return (uint32_t)__cvta_generic_to_shared(p); }
__device__ __forceinline__ void mbar_init(uint32_t bar, uint32_t cnt) {
  asm volatile("mbarrier.init.shared::cta.b64 [%0], %1;" ::"r"(bar), "r"(cnt) : "memory");
}
__device__ __forceinline__ void mbar_expect_tx(uint32_t bar, uint32_t bytes) {
  asm volatile("mbarrier.arrive.expect_tx.shared::cta.b64 _, [%0], %1;" ::"r"(bar), "r"(bytes) : "memory");
}
__device__ __forceinline__ bool mbar_try_wait(uint32_t bar, uint32_t parity) {
  uint32_t ok;
  asm volatile(
      "{\n.reg .pred p;\n"
      "mbarrier.try_wait.parity.shared::cta.b64 p, [%1], %2;\n"
      "selp.u32 %0, 1, 0, p;\n}\n"
      : "=r"(ok)
      : "r"(bar), "r"(parity)
      : "memory");
  return ok != 0;
}
__device__ __forceinline__ bool mbar_test_wait(uint32_t bar, uint32_t parity) {
  uint32_t ok;
  asm volatile(
      "{\n.reg .pred p;\n"
      "mbarrier.test_wait.parity.shared::cta.b64 p, [%1], %2;\n"
      "selp.u32 %0, 1, 0, p;\n}\n"
      : "=r"(ok)
      : "r"(bar), "r"(parity)
      : "memory");
  return ok != 0;
}
__device__ __forceinline__ bool spin_giveup(uint32_t& n, uint32_t abort_addr) {
  if ((++n & 0xFFFu) == 0) {
    uint32_t a;
    asm volatile("ld.volatile.shared.u32 %0, [%1];" : "=r"(a) : "r"(abort_addr) : "memory");
    if (a != 0 || n > (1u << 22)) {
      asm volatile("st.volatile.shared.u32 [%0], %1;" ::"r"(abort_addr), "r"(1u) : "memory");
      return true;
    }
  }
  return false;
}
__device__ __forceinline__ void mbar_wait(uint32_t bar, uint32_t parity, uint32_t abort_addr) {
  if (mbar_try_wait(bar, parity)) return;
  uint32_t n = 0;
  while (!mbar_try_wait(bar, parity)) {
    if (spin_giveup(n, abort_addr)) break;
  }
}
__device__ __forceinline__ void flag_wait(const unsigned int* f, unsigned int target, uint32_t abort_addr) {
  uint32_t n = 0;
  while (true) {
    unsigned int val;
    asm volatile("ld.acquire.gpu.global.u32 %0, [%1];" : "=r"(val) : "l"(f) : "memory");
    if ((int)(val - target) >= 0) break;
    if (spin_giveup(n, abort_addr)) break;
  }
}
__device__ __forceinline__ void mbar_arrive_local(uint32_t bar) {
  asm volatile("mbarrier.arrive.shared::cta.b64 _, [%0];" ::"r"(bar) : "memory");
}
__device__ __forceinline__ void mbar_arrive_remote(uint32_t cluster_addr) {
  asm volatile("mbarrier.arrive.shared::cluster.b64 _, [%0];" ::"r"(cluster_addr) : "memory");
}
__device__ __forceinline__ uint32_t mapa(uint32_t addr, uint32_t rank) {
  uint32_t r;
  asm volatile("mapa.shared::cluster.u32 %0, %1, %2;" : "=r"(r) : "r"(addr), "r"(rank));
  return r;
}
__device__ __forceinline__ void cluster_arrive_relaxed() { asm volatile("barrier.cluster.arrive.relaxed.aligned;" ::: "memory"); }
__device__ __forceinline__ void cluster_wait() { asm volatile("barrier.cluster.wait.acquire.aligned;" ::: "memory"); }

__device__ __forceinline__ void tma_2d_mc(uint32_t dst, const CUtensorMap* m, uint32_t bar, int c0, int c1, uint16_t mask) {
  asm volatile(
      "cp.async.bulk.tensor.2d.shared::cluster.global.mbarrier::complete_tx::bytes.multicast::cluster [%0], [%1, {%3, %4}], [%2], %5;"
      ::"r"(dst), "l"(m), "r"(bar), "r"(c0), "r"(c1), "h"(mask)
      : "memory");
}
__device__ __forceinline__ void tma_3d(uint32_t dst, const CUtensorMap* m, uint32_t bar, int c0, int c1, int c2) {
  asm volatile(
      "cp.async.bulk.tensor.3d.shared::cluster.global.mbarrier::complete_tx::bytes [%0], [%1, {%3, %4, %5}], [%2];"
      ::"r"(dst), "l"(m), "r"(bar), "r"(c0), "r"(c1), "r"(c2)
      : "memory");
}
__device__ __forceinline__ void tma_3d_hint(uint32_t dst, const CUtensorMap* m, uint32_t bar, int c0, int c1, int c2, uint64_t pol) {
  asm volatile(
      "cp.async.bulk.tensor.3d.shared::cluster.global.mbarrier::complete_tx::bytes.L2::cache_hint [%0], [%1, {%3, %4, %5}], [%2], %6;"
      ::"r"(dst), "l"(m), "r"(bar), "r"(c0), "r"(c1), "r"(c2), "l"(pol)
      : "memory");
}
__device__ __forceinline__ void tma_5d(uint32_t dst, const CUtensorMap* m, uint32_t bar, int c0, int c1, int c2, int c3, int c4) {
  asm volatile(
      "cp.async.bulk.tensor.5d.shared::cluster.global.mbarrier::complete_tx::bytes [%0], [%1, {%3, %4, %5, %6, %7}], [%2];"
      ::"r"(dst), "l"(m), "r"(bar), "r"(c0), "r"(c1), "r"(c2), "r"(c3), "r"(c4)
      : "memory");
}
__device__ __forceinline__ void prefetch_tmap(const CUtensorMap* m) {
  asm volatile("prefetch.tensormap [%0];" ::"l"(m) : "memory");
}

__device__ __forceinline__ uint32_t elect_one() {
  uint32_t pred = 0, laneid = 0;
  asm volatile(
      "{\n.reg .b32 %%rx;\n.reg .pred %%px;\n"
      "elect.sync %%rx|%%px, %2;\n"
      "@%%px mov.s32 %1, 1;\n"
      "mov.s32 %0, %%rx;\n}\n"
      : "+r"(laneid), "+r"(pred)
      : "r"(0xFFFFFFFFu));
  return pred;
}
__device__ __forceinline__ uint32_t clock32() {
  uint32_t c;
  asm volatile("mov.u32 %0, %%clock;" : "=r"(c));
  return c;
}

__device__ __forceinline__ void wg_fence() { asm volatile("wgmma.fence.sync.aligned;" ::: "memory"); }
__device__ __forceinline__ void wg_commit() { asm volatile("wgmma.commit_group.sync.aligned;" ::: "memory"); }
template <int N>
__device__ __forceinline__ void wg_wait() { asm volatile("wgmma.wait_group.sync.aligned %0;" ::"n"(N) : "memory"); }
template <int N>
__device__ __forceinline__ void fence_regs(float (&d)[N]) {
#pragma unroll
  for (int i = 0; i < N; i++) asm volatile("" : "+f"(d[i])::"memory");
}
template <int N>
__device__ __forceinline__ void fence_regs(uint32_t (&d)[N]) {
#pragma unroll
  for (int i = 0; i < N; i++) asm volatile("" : "+r"(d[i])::"memory");
}

constexpr uint32_t DESC_HI = (1024u >> 4) | (1u << 30);
constexpr uint32_t DESC_LO_K = (1u << 16);
constexpr uint32_t DESC_LO_MN = ((8192u >> 4) << 16);
__device__ __forceinline__ uint64_t mk_desc(uint32_t lo) { return ((uint64_t)DESC_HI << 32) | lo; }

__device__ __forceinline__ uint32_t pack_bf16(float lo, float hi) {
  uint32_t r;
  asm("cvt.rn.bf16x2.f32 %0, %1, %2;" : "=r"(r) : "f"(hi), "f"(lo));
  return r;
}
__device__ __forceinline__ float ex2(float x) {
  float r;
  asm("ex2.approx.ftz.f32 %0, %1;" : "=f"(r) : "f"(x));
  return r;
}

template <int TA, int TB> __device__ __forceinline__ void wgmma_ss_n64(float (&d)[32], uint64_t da, uint64_t db, int scale_d) {
  asm volatile("{\n.reg .pred p;\nsetp.ne.b32 p, %34, 0;\n"
    "wgmma.mma_async.sync.aligned.m64n64k16.f32.bf16.bf16 "
    "{%0, %1, %2, %3, %4, %5, %6, %7, %8, %9, %10, %11, %12, %13, %14, %15, %16, %17, %18, %19, %20, %21, %22, %23, %24, %25, %26, %27, %28, %29, %30, %31}, "
    "%32, %33, p, 1, 1, %35, %36;\n}\n"
    : "+f"(d[0]), "+f"(d[1]), "+f"(d[2]), "+f"(d[3]), "+f"(d[4]), "+f"(d[5]), "+f"(d[6]), "+f"(d[7]), "+f"(d[8]), "+f"(d[9]), "+f"(d[10]), "+f"(d[11]), "+f"(d[12]), "+f"(d[13]), "+f"(d[14]), "+f"(d[15]), "+f"(d[16]), "+f"(d[17]), "+f"(d[18]), "+f"(d[19]), "+f"(d[20]), "+f"(d[21]), "+f"(d[22]), "+f"(d[23]), "+f"(d[24]), "+f"(d[25]), "+f"(d[26]), "+f"(d[27]), "+f"(d[28]), "+f"(d[29]), "+f"(d[30]), "+f"(d[31])
    : "l"(da), "l"(db), "r"(scale_d), "n"(TA), "n"(TB));
}
template <int TB> __device__ __forceinline__ void wgmma_rs_n64(float (&d)[32], uint32_t a0, uint32_t a1, uint32_t a2, uint32_t a3, uint64_t db, int scale_d) {
  asm volatile("{\n.reg .pred p;\nsetp.ne.b32 p, %37, 0;\n"
    "wgmma.mma_async.sync.aligned.m64n64k16.f32.bf16.bf16 "
    "{%0, %1, %2, %3, %4, %5, %6, %7, %8, %9, %10, %11, %12, %13, %14, %15, %16, %17, %18, %19, %20, %21, %22, %23, %24, %25, %26, %27, %28, %29, %30, %31}, "
    "{%32, %33, %34, %35}, %36, p, 1, 1, %38;\n}\n"
    : "+f"(d[0]), "+f"(d[1]), "+f"(d[2]), "+f"(d[3]), "+f"(d[4]), "+f"(d[5]), "+f"(d[6]), "+f"(d[7]), "+f"(d[8]), "+f"(d[9]), "+f"(d[10]), "+f"(d[11]), "+f"(d[12]), "+f"(d[13]), "+f"(d[14]), "+f"(d[15]), "+f"(d[16]), "+f"(d[17]), "+f"(d[18]), "+f"(d[19]), "+f"(d[20]), "+f"(d[21]), "+f"(d[22]), "+f"(d[23]), "+f"(d[24]), "+f"(d[25]), "+f"(d[26]), "+f"(d[27]), "+f"(d[28]), "+f"(d[29]), "+f"(d[30]), "+f"(d[31])
    : "r"(a0), "r"(a1), "r"(a2), "r"(a3), "l"(db), "r"(scale_d), "n"(TB));
}
template <int TB> __device__ __forceinline__ void wgmma_rs_n64_z(float (&d)[32], uint32_t a0, uint32_t a1, uint32_t a2, uint32_t a3, uint64_t db) {
  asm volatile("{\n.reg .pred p;\nsetp.ne.b32 p, 0, 0;\n"
    "wgmma.mma_async.sync.aligned.m64n64k16.f32.bf16.bf16 "
    "{%0, %1, %2, %3, %4, %5, %6, %7, %8, %9, %10, %11, %12, %13, %14, %15, %16, %17, %18, %19, %20, %21, %22, %23, %24, %25, %26, %27, %28, %29, %30, %31}, "
    "{%32, %33, %34, %35}, %36, p, 1, 1, %37;\n}\n"
    : "=f"(d[0]), "=f"(d[1]), "=f"(d[2]), "=f"(d[3]), "=f"(d[4]), "=f"(d[5]), "=f"(d[6]), "=f"(d[7]), "=f"(d[8]), "=f"(d[9]), "=f"(d[10]), "=f"(d[11]), "=f"(d[12]), "=f"(d[13]), "=f"(d[14]), "=f"(d[15]), "=f"(d[16]), "=f"(d[17]), "=f"(d[18]), "=f"(d[19]), "=f"(d[20]), "=f"(d[21]), "=f"(d[22]), "=f"(d[23]), "=f"(d[24]), "=f"(d[25]), "=f"(d[26]), "=f"(d[27]), "=f"(d[28]), "=f"(d[29]), "=f"(d[30]), "=f"(d[31])
    : "r"(a0), "r"(a1), "r"(a2), "r"(a3), "l"(db), "n"(TB));
}
template <int TA, int TB> __device__ __forceinline__ void wgmma_ss_n128(float (&d)[64], uint64_t da, uint64_t db, int scale_d) {
  asm volatile("{\n.reg .pred p;\nsetp.ne.b32 p, %66, 0;\n"
    "wgmma.mma_async.sync.aligned.m64n128k16.f32.bf16.bf16 "
    "{%0, %1, %2, %3, %4, %5, %6, %7, %8, %9, %10, %11, %12, %13, %14, %15, %16, %17, %18, %19, %20, %21, %22, %23, %24, %25, %26, %27, %28, %29, %30, %31, %32, %33, %34, %35, %36, %37, %38, %39, %40, %41, %42, %43, %44, %45, %46, %47, %48, %49, %50, %51, %52, %53, %54, %55, %56, %57, %58, %59, %60, %61, %62, %63}, "
    "%64, %65, p, 1, 1, %67, %68;\n}\n"
    : "+f"(d[0]), "+f"(d[1]), "+f"(d[2]), "+f"(d[3]), "+f"(d[4]), "+f"(d[5]), "+f"(d[6]), "+f"(d[7]), "+f"(d[8]), "+f"(d[9]), "+f"(d[10]), "+f"(d[11]), "+f"(d[12]), "+f"(d[13]), "+f"(d[14]), "+f"(d[15]), "+f"(d[16]), "+f"(d[17]), "+f"(d[18]), "+f"(d[19]), "+f"(d[20]), "+f"(d[21]), "+f"(d[22]), "+f"(d[23]), "+f"(d[24]), "+f"(d[25]), "+f"(d[26]), "+f"(d[27]), "+f"(d[28]), "+f"(d[29]), "+f"(d[30]), "+f"(d[31]), "+f"(d[32]), "+f"(d[33]), "+f"(d[34]), "+f"(d[35]), "+f"(d[36]), "+f"(d[37]), "+f"(d[38]), "+f"(d[39]), "+f"(d[40]), "+f"(d[41]), "+f"(d[42]), "+f"(d[43]), "+f"(d[44]), "+f"(d[45]), "+f"(d[46]), "+f"(d[47]), "+f"(d[48]), "+f"(d[49]), "+f"(d[50]), "+f"(d[51]), "+f"(d[52]), "+f"(d[53]), "+f"(d[54]), "+f"(d[55]), "+f"(d[56]), "+f"(d[57]), "+f"(d[58]), "+f"(d[59]), "+f"(d[60]), "+f"(d[61]), "+f"(d[62]), "+f"(d[63])
    : "l"(da), "l"(db), "r"(scale_d), "n"(TA), "n"(TB));
}
template <int TB> __device__ __forceinline__ void wgmma_rs_n128(float (&d)[64], uint32_t a0, uint32_t a1, uint32_t a2, uint32_t a3, uint64_t db, int scale_d) {
  asm volatile("{\n.reg .pred p;\nsetp.ne.b32 p, %69, 0;\n"
    "wgmma.mma_async.sync.aligned.m64n128k16.f32.bf16.bf16 "
    "{%0, %1, %2, %3, %4, %5, %6, %7, %8, %9, %10, %11, %12, %13, %14, %15, %16, %17, %18, %19, %20, %21, %22, %23, %24, %25, %26, %27, %28, %29, %30, %31, %32, %33, %34, %35, %36, %37, %38, %39, %40, %41, %42, %43, %44, %45, %46, %47, %48, %49, %50, %51, %52, %53, %54, %55, %56, %57, %58, %59, %60, %61, %62, %63}, "
    "{%64, %65, %66, %67}, %68, p, 1, 1, %70;\n}\n"
    : "+f"(d[0]), "+f"(d[1]), "+f"(d[2]), "+f"(d[3]), "+f"(d[4]), "+f"(d[5]), "+f"(d[6]), "+f"(d[7]), "+f"(d[8]), "+f"(d[9]), "+f"(d[10]), "+f"(d[11]), "+f"(d[12]), "+f"(d[13]), "+f"(d[14]), "+f"(d[15]), "+f"(d[16]), "+f"(d[17]), "+f"(d[18]), "+f"(d[19]), "+f"(d[20]), "+f"(d[21]), "+f"(d[22]), "+f"(d[23]), "+f"(d[24]), "+f"(d[25]), "+f"(d[26]), "+f"(d[27]), "+f"(d[28]), "+f"(d[29]), "+f"(d[30]), "+f"(d[31]), "+f"(d[32]), "+f"(d[33]), "+f"(d[34]), "+f"(d[35]), "+f"(d[36]), "+f"(d[37]), "+f"(d[38]), "+f"(d[39]), "+f"(d[40]), "+f"(d[41]), "+f"(d[42]), "+f"(d[43]), "+f"(d[44]), "+f"(d[45]), "+f"(d[46]), "+f"(d[47]), "+f"(d[48]), "+f"(d[49]), "+f"(d[50]), "+f"(d[51]), "+f"(d[52]), "+f"(d[53]), "+f"(d[54]), "+f"(d[55]), "+f"(d[56]), "+f"(d[57]), "+f"(d[58]), "+f"(d[59]), "+f"(d[60]), "+f"(d[61]), "+f"(d[62]), "+f"(d[63])
    : "r"(a0), "r"(a1), "r"(a2), "r"(a3), "l"(db), "r"(scale_d), "n"(TB));
}
template <int TA, int TB> __device__ __forceinline__ void wgmma_ss_n160(float (&d)[80], uint64_t da, uint64_t db, int scale_d) {
  asm volatile("{\n.reg .pred p;\nsetp.ne.b32 p, %82, 0;\n"
    "wgmma.mma_async.sync.aligned.m64n160k16.f32.bf16.bf16 "
    "{%0, %1, %2, %3, %4, %5, %6, %7, %8, %9, %10, %11, %12, %13, %14, %15, %16, %17, %18, %19, %20, %21, %22, %23, %24, %25, %26, %27, %28, %29, %30, %31, %32, %33, %34, %35, %36, %37, %38, %39, %40, %41, %42, %43, %44, %45, %46, %47, %48, %49, %50, %51, %52, %53, %54, %55, %56, %57, %58, %59, %60, %61, %62, %63, %64, %65, %66, %67, %68, %69, %70, %71, %72, %73, %74, %75, %76, %77, %78, %79}, "
    "%80, %81, p, 1, 1, %83, %84;\n}\n"
    : "+f"(d[0]), "+f"(d[1]), "+f"(d[2]), "+f"(d[3]), "+f"(d[4]), "+f"(d[5]), "+f"(d[6]), "+f"(d[7]), "+f"(d[8]), "+f"(d[9]), "+f"(d[10]), "+f"(d[11]), "+f"(d[12]), "+f"(d[13]), "+f"(d[14]), "+f"(d[15]), "+f"(d[16]), "+f"(d[17]), "+f"(d[18]), "+f"(d[19]), "+f"(d[20]), "+f"(d[21]), "+f"(d[22]), "+f"(d[23]), "+f"(d[24]), "+f"(d[25]), "+f"(d[26]), "+f"(d[27]), "+f"(d[28]), "+f"(d[29]), "+f"(d[30]), "+f"(d[31]), "+f"(d[32]), "+f"(d[33]), "+f"(d[34]), "+f"(d[35]), "+f"(d[36]), "+f"(d[37]), "+f"(d[38]), "+f"(d[39]), "+f"(d[40]), "+f"(d[41]), "+f"(d[42]), "+f"(d[43]), "+f"(d[44]), "+f"(d[45]), "+f"(d[46]), "+f"(d[47]), "+f"(d[48]), "+f"(d[49]), "+f"(d[50]), "+f"(d[51]), "+f"(d[52]), "+f"(d[53]), "+f"(d[54]), "+f"(d[55]), "+f"(d[56]), "+f"(d[57]), "+f"(d[58]), "+f"(d[59]), "+f"(d[60]), "+f"(d[61]), "+f"(d[62]), "+f"(d[63]), "+f"(d[64]), "+f"(d[65]), "+f"(d[66]), "+f"(d[67]), "+f"(d[68]), "+f"(d[69]), "+f"(d[70]), "+f"(d[71]), "+f"(d[72]), "+f"(d[73]), "+f"(d[74]), "+f"(d[75]), "+f"(d[76]), "+f"(d[77]), "+f"(d[78]), "+f"(d[79])
    : "l"(da), "l"(db), "r"(scale_d), "n"(TA), "n"(TB));
}

__global__ void __cluster_dims__(2, 1, 1) __launch_bounds__(NTHREADS, 1)
gqa_fused_kernel(const __grid_constant__ Maps maps, __nv_bfloat16* __restrict__ out) {
  extern __shared__ __align__(1024) uint8_t smem_raw[];
  const uint32_t smem0 = smem_u32(smem_raw);
  const uint32_t sbase = (smem0 + 1023u) & ~1023u;
  const uint32_t bar_gf = sbase + OFF_BAR;
  const uint32_t bar_ge = bar_gf + 4 * 8;
  const uint32_t bar_kf = bar_ge + 4 * 8;
  const uint32_t bar_ke = bar_kf + 11 * 8;
  const uint32_t bar_of = bar_ke + NKV * 8;
  const uint32_t bar_oe = bar_of + 4 * 8;
  const uint32_t bar_pub = bar_oe + 4 * 8;
  const uint32_t bar_kgo = bar_pub + 8;
  const uint32_t bar_kgo2 = bar_kgo + 8;
  const uint32_t abort_addr = bar_kgo2 + 8;
  const uint32_t epoch_addr = abort_addr + 12;

  const int tid = threadIdx.x;
  const int warp = __shfl_sync(0xffffffffu, tid >> 5, 0);
  const int lane = tid & 31;
  const int cta = blockIdx.x;
  const int rank = cta & 1;
  const int u = (cta >> 1) & 3;
  const int b = cta >> 3;

  unsigned int obase = 0;
  if (tid == 0) PROF(3, 0);
  if (tid == 0) {
    for (uint32_t i = 0; i < 4; i++) { mbar_init(bar_gf + i * 8, 1); mbar_init(bar_ge + i * 8, 24); }
    mbar_init(bar_kgo, 12);
    mbar_init(bar_kgo2, 12);
    for (uint32_t i = 0; i < 11; i++) mbar_init(bar_kf + i * 8, 1);
    for (uint32_t i = 0; i < NKV; i++) mbar_init(bar_ke + i * 8, 12);
    for (uint32_t i = 0; i < 4; i++) { mbar_init(bar_of + i * 8, 1); mbar_init(bar_oe + i * 8, 24); }
    mbar_init(bar_pub, 12);
    asm volatile("st.shared.u32 [%0], %1;" ::"r"(abort_addr), "r"(0u) : "memory");
    asm volatile("fence.mbarrier_init.release.cluster;" ::: "memory");
  }
  if (warp == 13 && lane == 0) {
    prefetch_tmap(&maps.x);
    prefetch_tmap(&maps.wq);
    prefetch_tmap(&maps.k);
    prefetch_tmap(&maps.v);
    obase = *(volatile unsigned int*)&g_oflag[b * NH + 2 * u + rank];
  }
  obase = __shfl_sync(0xffffffffu, obase, 0);
  cluster_arrive_relaxed();
  cluster_wait();

  if (warp >= 12) {
    asm volatile("setmaxnreg.dec.sync.aligned.u32 32;");
    if (warp == 12 && elect_one()) {
      uint64_t pol_stream;
      asm volatile("createpolicy.fractional.L2::evict_first.b64 %0, 1.0;" : "=l"(pol_stream));
      uint32_t next = clock32() + KV_START + (uint32_t)(cta & 63) * (KV_T / 64) + (u >= 2 ? STAG_D : 0);
#pragma unroll 1
      for (int n = 0; n < 64; n++) {
        TRACE(0, n);
        const uint32_t kit = n >> 4, kj = n & 15;
        if (kj == 3) mbar_wait(bar_kgo, kit & 1, abort_addr);
        if (kj == 6) mbar_wait(bar_kgo2, kit & 1, abort_addr);
        if (kj >= 11) mbar_wait(bar_ke + (kj - 11) * 8, 0, abort_addr);
        if (kj < 3 && kit > 0) mbar_wait(bar_ke + kj * 8, 1, abort_addr);
        if (n >= KV_OUT) {
          const uint32_t m = n - KV_OUT;
          mbar_wait(bar_kf + tile_bar(m & 15) * 8, tile_par(m & 15, m >> 4), abort_addr);
        }
        const uint32_t fb = bar_kf + tile_bar(kj) * 8;
        uint32_t now;
        while ((int)((now = clock32()) - next) < 0) { if (SPIN_NS) __nanosleep(SPIN_NS); }
        next = ((int)(now - next) > KV_T / 2 ? now : next) + KV_T;
        const int h = 8 * (n >> 4) + 2 * u + rank;
        const int row = (b * NH + h) * SK + ((n & 15) >> 1) * 64;
        mbar_expect_tx(fb, SZ_KV);
        tma_3d_hint(sbase + tile_off(kj), (n & 1) ? &maps.v : &maps.k, fb, 0, row, 0, pol_stream);
        TRACE(1, n);
      }
      PROF(3, 19);
    } else if (warp == 13 && elect_one()) {
      asm volatile("st.volatile.shared.u32 [%0], %1;" ::"r"(epoch_addr), "r"(obase + 1) : "memory");
      if (STAG_D > 0 && u >= 2) { const uint32_t t0 = clock32(); while ((int)(clock32() - t0) < STAG_D) __nanosleep(200); }
#pragma unroll 1
      for (int it = 0; it < 4; it++) {
        const int h = 8 * it + 2 * u + rank;
#pragma unroll 1
        for (int kb = 0; kb < 10; kb++) {
          const uint32_t slot = kb & 3;
          const uint32_t use = (slot < 2 ? it * 3 : it * 2) + (kb >> 2);
          TRACE(3, it * 10 + kb);
          if (use > 0) mbar_wait(bar_ge + slot * 8, (use - 1) & 1, abort_addr);
          const uint32_t dst = sbase + (slot == 3 ? OFF_QP3 : slot * SZ_QP), fb = bar_gf + slot * 8;
          mbar_expect_tx(fb, SZ_QP);
          tma_2d_mc(dst + 16384 + rank * 12288, &maps.x, fb, kb * 64, b * SQ + rank * 96, (uint16_t)3);
          tma_3d(dst, &maps.wq, fb, 0, kb * 64, 2 * h);
          TRACE(4, it * 10 + kb);
        }
        PROF(3, 1 + it * 4);
      }
      const int c = 2 * (u & 1) + rank;
      const int kh = u >> 1;
      const CUtensorMap* wo = &maps.wo[c];
      prefetch_tmap(&maps.o);
      prefetch_tmap(wo);
      const unsigned int otarget = obase + 1;
      const int nst = kh == 0 ? 32 + NX : 32 - NX;
#pragma unroll 1
      for (int kb = 0; kb < nst; kb++) {
        int sidx, grp;
        if (kh == 0) {
          if (kb < 24) { sidx = kb; grp = 0; }
          else if (kb < 24 + NX) { sidx = kb - 24; grp = 4; }
          else { sidx = kb - NX; grp = 0; }
        } else { sidx = kb + NX; grp = 4; }
        const int hi = sidx >> 1, t = sidx & 1;
        const int hh = 8 * (hi >> 2) + grp + (hi & 3);
        const uint32_t slot = kb & 3;
        TRACE(3, 40 + kb);
        if (t == 0 || kb == 0) {
          flag_wait(&g_oflag[b * NH + hh], otarget, abort_addr);
          asm volatile("fence.proxy.async.global;" ::: "memory");
        }
        mbar_wait(bar_oe + slot * 8, (kb >> 2) & 1, abort_addr);
        const uint32_t dst = sbase + slot * SZ_OP, fb = bar_of + slot * 8;
        mbar_expect_tx(fb, SZ_OP);
        tma_2d_mc(dst + rank * 12288, &maps.o, fb, 0, ((b * NH + hh) * 2 + t) * SQ + rank * 96, (uint16_t)3);
        tma_5d(dst + 24576, wo, fb, 0, 0, 0, 8 * t, hh);
        tma_5d(dst + 24576 + 8192, wo, fb, 64, 0, 0, 8 * t, hh);
        tma_5d(dst + 24576 + 16384, wo, fb, 128, 0, 0, 8 * t, hh);
        TRACE(4, 40 + kb);
      }
      PROF(3, 20);
    } else if (warp == 14 && elect_one()) {
#pragma unroll 1
      for (int oit = 0; oit < 4; oit++) {
        uint32_t spins = 0;
        while (!mbar_test_wait(bar_pub, oit & 1)) {
          __nanosleep(SPIN_NS);
          if (spin_giveup(spins, abort_addr)) break;
        }
        asm volatile("fence.acq_rel.gpu;" ::: "memory");
        asm volatile("red.relaxed.gpu.global.add.u32 [%0], 1;" ::"l"(&g_oflag[b * NH + 8 * oit + 2 * u + rank]) : "memory");
      }
    }
    __syncwarp();
    cluster_arrive_relaxed();
    cluster_wait();
  } else {
    asm volatile("setmaxnreg.inc.sync.aligned.u32 160;");
    const int wg = warp >> 2;
    const uint32_t sd = __shfl_sync(0xffffffffu, sbase & 0x3FFFFu, 0);
    auto uni = [](uint32_t v) { return __shfl_sync(0xffffffffu, v, 0); };
    auto release2 = [&](uint32_t eb) {
      if (lane == 0) {
        mbar_arrive_local(eb);
        mbar_arrive_remote(mapa(eb, rank ^ 1));
      }
    };
    const float cexp = 0.08838834764831845f * 1.4426950408889634f;
    const int q4 = lane & 3;
    const int rowl = wg * 64 + (warp & 3) * 16 + (lane >> 2);

    auto turn_begin = [&]() {
      asm volatile("bar.sync %0, 256;" ::"r"(wg + 1) : "memory");
    };
    auto turn_end = [&]() {
      asm volatile("bar.arrive %0, 256;" ::"r"(wg == 2 ? 1 : wg + 2) : "memory");
    };
    if (wg == 2) turn_end();
    const bool plead = ((warp & 3) == 0) && lane == 0;
    if (plead) PROF(wg, 0);
    uint4 opk[8];
    uint4* optr = reinterpret_cast<uint4*>(g_o) + (size_t)(b * NH + 2 * u + rank - 8) * (2 * SQ * 8) + rowl * 8 + q4;
    auto o_store = [&](int j) {
      optr[((j >> 2) * SQ) * 8 + ((j >> 1) & 1) * 4 + (j & 1) * 64] = opk[j];
      if (j == 7) {
        asm volatile("fence.proxy.async.global;" ::: "memory");
        __syncwarp();
        if (lane == 0) mbar_arrive_local(bar_pub);
      }
    };
#pragma unroll
    for (int j = 0; j < 8; j++) opk[j] = make_uint4(0u, 0u, 0u, 0u);
    for (int it = 0; it < 4; it++) {
      uint32_t qf[4 * QRS];
      {
        float acc[64];
#pragma unroll
        for (int i = 0; i < 64; i++) acc[i] = 0.f;
#pragma unroll
        for (int kb = 0; kb < 10; kb++) {
          const uint32_t slot = kb & 3;
          const uint32_t use = (slot < 2 ? it * 3 : it * 2) + (kb >> 2);
          const uint32_t st = sd + (slot == 3 ? OFF_QP3 : slot * SZ_QP);
          const uint32_t alo = uni(DESC_LO_K | ((st + 16384 + wg * 8192) >> 4));
          const uint32_t blo = uni(DESC_LO_MN | (st >> 4));
          mbar_wait(bar_gf + slot * 8, use & 1, abort_addr);
          wg_fence();
#pragma unroll
          for (int ks = 0; ks < 4; ks++)
            wgmma_ss_n128<0, 1>(acc, mk_desc(alo + ks * 2), mk_desc(blo + ks * 128), 1);
          wg_commit();
          if (kb < 8 && it > 0) o_store(kb);
          auto rel = [&](int k) {
            if (k == 7) { if (lane == 0) mbar_arrive_local(bar_kgo); }
            else if (k == 9) { if (lane == 0) mbar_arrive_local(bar_kgo2); }
            else if (k != 6 && k != 8) release2(bar_ge + (k & 3) * 8);
          };
          wg_wait<0>();
          rel(kb);
        }
        fence_regs(acc);
#pragma unroll
        for (int i = 0; i < 4 * QRS; i++) qf[i] = pack_bf16(acc[2 * i], acc[2 * i + 1]);
        {
          const uint32_t qrow = sbase + OFF_QS + rowl * 128 + q4 * 4;
          const uint32_t sw = (uint32_t)(lane >> 2);
#pragma unroll
          for (int cch = 2 * (QRS - 4); cch < 8; cch++) {
            const uint32_t a = qrow + ((cch ^ sw) << 4);
            asm volatile("st.shared.b32 [%0], %1;" ::"r"(a), "r"(pack_bf16(acc[32 + 4 * cch], acc[33 + 4 * cch])) : "memory");
            asm volatile("st.shared.b32 [%0], %1;" ::"r"(a + 1024), "r"(pack_bf16(acc[34 + 4 * cch], acc[35 + 4 * cch])) : "memory");
          }
          asm volatile("fence.proxy.async.shared::cta;" ::: "memory");
          asm volatile("bar.sync %0, 128;" ::"r"(wg + 4) : "memory");
        }
      }
      if (plead) PROF(wg, 1 + it * 4);
      float o[64];
#pragma unroll
      for (int i = 0; i < 64; i++) o[i] = 0.f;
      float m0, m1, l0, l1;
      float sa[32];
      uint32_t pf[16];
      const uint32_t qlo = uni(DESC_LO_K | ((sd + OFF_QS + wg * 8192) >> 4));
      auto issue_qk = [&](uint32_t klo) {
        wgmma_rs_n64_z<0>(sa, qf[0], qf[1], qf[2], qf[3], mk_desc(klo));
#pragma unroll
        for (int ks = 1; ks < QRS; ks++)
          wgmma_rs_n64<0>(sa, qf[4 * ks], qf[4 * ks + 1], qf[4 * ks + 2], qf[4 * ks + 3], mk_desc(klo + (ks >> 2) * 512 + (ks & 3) * 2), 1);
#pragma unroll
        for (int ks = QRS - 4; ks < 4; ks++)
          wgmma_ss_n64<0, 0>(sa, mk_desc(qlo + ks * 2), mk_desc(klo + 512 + ks * 2), 1);
        wg_commit();
      };
      auto issue_pv = [&](uint32_t vlo) {
#pragma unroll
        for (int ks = 0; ks < 4; ks++)
          wgmma_rs_n128<1>(o, pf[4 * ks], pf[4 * ks + 1], pf[4 * ks + 2], pf[4 * ks + 3], mk_desc(vlo + ks * 128), 1);
        wg_commit();
      };
      auto row_max = [&](float& mx0, float& mx1) {
        mx0 = fmaxf(sa[0], sa[1]);
        mx1 = fmaxf(sa[2], sa[3]);
#pragma unroll
        for (int i = 1; i < 8; i++) {
          mx0 = fmaxf(mx0, fmaxf(sa[4 * i], sa[4 * i + 1]));
          mx1 = fmaxf(mx1, fmaxf(sa[4 * i + 2], sa[4 * i + 3]));
        }
        mx0 = fmaxf(mx0, __shfl_xor_sync(0xffffffffu, mx0, 1));
        mx1 = fmaxf(mx1, __shfl_xor_sync(0xffffffffu, mx1, 1));
        mx0 = fmaxf(mx0, __shfl_xor_sync(0xffffffffu, mx0, 2));
        mx1 = fmaxf(mx1, __shfl_xor_sync(0xffffffffu, mx1, 2));
        mx0 *= cexp;
        mx1 *= cexp;
      };
      auto exp_pack = [&](float& b0, float& b1) {
        b0 = 0.f; b1 = 0.f;
#pragma unroll
        for (int i = 0; i < 8; i++) {
          const float p0 = ex2(fmaf(sa[4 * i], cexp, -m0)), p1 = ex2(fmaf(sa[4 * i + 1], cexp, -m0));
          const float p2 = ex2(fmaf(sa[4 * i + 2], cexp, -m1)), p3 = ex2(fmaf(sa[4 * i + 3], cexp, -m1));
          pf[2 * i] = pack_bf16(p0, p1);
          pf[2 * i + 1] = pack_bf16(p2, p3);
          b0 += p0 + p1;
          b1 += p2 + p3;
        }
      };
      auto k_desc = [&](uint32_t j) { return uni(DESC_LO_K | ((sd + tile_off(j)) >> 4)); };
      auto v_desc = [&](uint32_t j) { return uni(DESC_LO_MN | ((sd + tile_off(j)) >> 4)); };
      auto kv_release = [&](uint32_t j) { if (lane == 0 && (j < 5 || j >= 11)) mbar_arrive_local(bar_ke + tile_bar(j) * 8); };
      auto kv_wait = [&](uint32_t j) { mbar_wait(bar_kf + tile_bar(j) * 8, tile_par(j, it), abort_addr); };
      {
        const uint32_t kd = k_desc(0);
        kv_wait(0);
        turn_begin();
        wg_fence();
        issue_qk(kd);
        turn_end();
        wg_wait<0>();
        fence_regs(sa);
        kv_release(0);
        row_max(m0, m1);
        exp_pack(l0, l1);
      }
#pragma unroll AT_UNROLL
      for (int t = 1; t < 8; t++) {
        const uint32_t sv = 2 * t - 1, sk = 2 * t;
        const uint32_t vd = v_desc(sv), kd = k_desc(sk);
        PROF2(wg, t * 6);
        kv_wait(sv);
        kv_wait(sk);
        PROF2(wg, t * 6 + 1);
        fence_regs(pf);
        fence_regs(o);
        turn_begin();
        wg_fence();
        issue_pv(vd);
        issue_qk(kd);
        turn_end();
        PROF2(wg, t * 6 + 4);
        wg_wait<0>();
        fence_regs(sa);
        fence_regs(o);
        fence_regs(pf);
        PROF2(wg, t * 6 + 2);
        kv_release(sv);
        kv_release(sk);
        if (t == 4) release2(it == 3 ? bar_oe : bar_ge);
        if (t == 5) release2(it == 3 ? bar_oe + 8 : bar_ge + 8);
        if (t == 7) release2(bar_ge + 2 * 8);
        float b0, b1;
        exp_pack(b0, b1);
        if (__any_sync(0xffffffffu, !(b0 <= 1024.f) || !(b1 <= 1024.f))) {
          float mx0, mx1;
          row_max(mx0, mx1);
          mx0 = fmaxf(mx0, m0);
          mx1 = fmaxf(mx1, m1);
          const float sc0 = ex2(m0 - mx0), sc1 = ex2(m1 - mx1);
          m0 = mx0; m1 = mx1;
          l0 *= sc0; l1 *= sc1;
#pragma unroll
          for (int i = 0; i < 16; i++) {
            o[4 * i] *= sc0; o[4 * i + 1] *= sc0;
            o[4 * i + 2] *= sc1; o[4 * i + 3] *= sc1;
          }
          exp_pack(b0, b1);
        }
        l0 += b0;
        l1 += b1;
        PROF2(wg, t * 6 + 3);
      }
      {
        const uint32_t sv = 15;
        const uint32_t vd = v_desc(sv);
        kv_wait(sv);
        fence_regs(pf);
        fence_regs(o);
        turn_begin();
        wg_fence();
        issue_pv(vd);
        turn_end();
        wg_wait<0>();
        fence_regs(o);
        kv_release(sv);
        if (it == 3) { release2(bar_oe + 16); release2(bar_oe + 24); }
        else release2(bar_ge + 3 * 8);
      }
      if (plead) PROF(wg, 2 + it * 4);
      l0 += __shfl_xor_sync(0xffffffffu, l0, 1);
      l1 += __shfl_xor_sync(0xffffffffu, l1, 1);
      l0 += __shfl_xor_sync(0xffffffffu, l0, 2);
      l1 += __shfl_xor_sync(0xffffffffu, l1, 2);
      const float i0 = 1.0f / l0, i1 = 1.0f / l1;
#pragma unroll
      for (int J = 0; J < 4; J++) {
        uint4& v0 = opk[2 * J];
        uint4& v1 = opk[2 * J + 1];
        v0.x = pack_bf16(o[4 * J] * i0, o[4 * J + 1] * i0);
        v0.y = pack_bf16(o[4 * (J + 4)] * i0, o[4 * (J + 4) + 1] * i0);
        v0.z = pack_bf16(o[4 * (J + 8)] * i0, o[4 * (J + 8) + 1] * i0);
        v0.w = pack_bf16(o[4 * (J + 12)] * i0, o[4 * (J + 12) + 1] * i0);
        v1.x = pack_bf16(o[4 * J + 2] * i1, o[4 * J + 3] * i1);
        v1.y = pack_bf16(o[4 * (J + 4) + 2] * i1, o[4 * (J + 4) + 3] * i1);
        v1.z = pack_bf16(o[4 * (J + 8) + 2] * i1, o[4 * (J + 8) + 3] * i1);
        v1.w = pack_bf16(o[4 * (J + 12) + 2] * i1, o[4 * (J + 12) + 3] * i1);
      }
      optr += (size_t)8 * (2 * SQ * 8);
      if (plead) PROF(wg, 3 + it * 4);
    }
    {
      float acc[80];
#pragma unroll
      for (int i = 0; i < 80; i++) acc[i] = 0.f;
      auto op_stage = [&](int kb, int j) {
        const uint32_t slot = kb & 3;
        const uint32_t st = sd + slot * SZ_OP;
        const uint32_t alo = uni(DESC_LO_K | ((st + wg * 8192) >> 4));
        const uint32_t blo = uni(DESC_LO_MN | ((st + 24576) >> 4));
        mbar_wait(bar_of + slot * 8, (kb >> 2) & 1, abort_addr);
        wg_fence();
#pragma unroll
        for (int ks = 0; ks < 4; ks++)
          wgmma_ss_n160<0, 1>(acc, mk_desc(alo + ks * 2), mk_desc(blo + ks * 128), 1);
        wg_commit();
        if (j >= 0) o_store(j);
        wg_wait<0>();
        release2(bar_oe + slot * 8);
      };
      const int kh = u >> 1;
      const int nst = kh == 0 ? 32 + NX : 32 - NX;
      const int c = 2 * (u & 1) + rank;
      const int pid = b * 4 + c;
      float4* part = g_part + (size_t)pid * (20 * 384) + (wg * 128 + (warp & 3) * 32 + lane);
      unsigned int* xflag = &g_xflag[pid * 12 + warp];
#pragma unroll
      for (int kb = 0; kb < 8; kb++) op_stage(kb, kb);
#pragma unroll 1
      for (int kb = 8; kb < nst - 1; kb++) op_stage(kb, -1);
      if (kh == 0) {
        op_stage(nst - 1, -1);
        fence_regs(acc);
        if (plead) PROF(wg, 20);
#pragma unroll
        for (int i = 0; i < 20; i++) __stcg(part + i * 384, make_float4(acc[4 * i], acc[4 * i + 1], acc[4 * i + 2], acc[4 * i + 3]));
        asm volatile("fence.acq_rel.gpu;" ::: "memory");
        __syncwarp();
        if (lane == 0) asm volatile("red.relaxed.gpu.global.add.u32 [%0], 1;" ::"l"(xflag) : "memory");
      } else {
        if (lane == 0) {
          uint32_t target;
          asm volatile("ld.volatile.shared.u32 %0, [%1];" : "=r"(target) : "r"(epoch_addr) : "memory");
          flag_wait(xflag, target, abort_addr);
        }
        __syncwarp();
        float4 tp[12], tq[8];
#pragma unroll
        for (int i = 0; i < 12; i++) tp[i] = __ldcg(part + i * 384);
        op_stage(nst - 1, -1);
        fence_regs(acc);
        if (plead) PROF(wg, 20);
#pragma unroll
        for (int i = 0; i < 48; i += 4) { acc[i] += tp[i >> 2].x; acc[i + 1] += tp[i >> 2].y; acc[i + 2] += tp[i >> 2].z; acc[i + 3] += tp[i >> 2].w; }
#pragma unroll
        for (int i = 0; i < 8; i++) tq[i] = __ldcg(part + (12 + i) * 384);
        uint4* orow0 = reinterpret_cast<uint4*>(out + (size_t)(b * SQ + rowl) * DM + c * 160 + 8 * q4);
        uint4* orow1 = orow0 + 8 * (DM / 8);
        auto transpose4 = [&](uint32_t (&w)[4]) {
          const bool o1 = (q4 & 1) != 0, o2 = (q4 & 2) != 0;
          uint32_t s0 = __shfl_xor_sync(0xffffffffu, o1 ? w[0] : w[1], 1);
          uint32_t s1 = __shfl_xor_sync(0xffffffffu, o1 ? w[2] : w[3], 1);
          if (o1) { w[0] = s0; w[2] = s1; } else { w[1] = s0; w[3] = s1; }
          s0 = __shfl_xor_sync(0xffffffffu, o2 ? w[0] : w[2], 2);
          s1 = __shfl_xor_sync(0xffffffffu, o2 ? w[1] : w[3], 2);
          if (o2) { w[0] = s0; w[1] = s1; } else { w[2] = s0; w[3] = s1; }
        };
#pragma unroll
        for (int g = 0; g < 5; g++) {
          uint32_t w0[4], w1[4];
#pragma unroll
          for (int j = 0; j < 4; j++) {
            const int i = g * 4 + j;
            if (g < 3) {
              w0[j] = pack_bf16(acc[4 * i], acc[4 * i + 1]);
              w1[j] = pack_bf16(acc[4 * i + 2], acc[4 * i + 3]);
            } else {
              const float4 t = tq[i - 12];
              w0[j] = pack_bf16(acc[4 * i] + t.x, acc[4 * i + 1] + t.y);
              w1[j] = pack_bf16(acc[4 * i + 2] + t.z, acc[4 * i + 3] + t.w);
            }
          }
          transpose4(w0);
          transpose4(w1);
          orow0[g * 4] = make_uint4(w0[0], w0[1], w0[2], w0[3]);
          orow1[g * 4] = make_uint4(w1[0], w1[1], w1[2], w1[3]);
        }
      }
    }
    if (plead) PROF(wg, 21);
    cluster_arrive_relaxed();
    cluster_wait();
  }
}

typedef CUresult (*EncodeFn)(CUtensorMap*, CUtensorMapDataType, cuuint32_t, void*, const cuuint64_t*, const cuuint64_t*,
                             const cuuint32_t*, const cuuint32_t*, CUtensorMapInterleave, CUtensorMapSwizzle,
                             CUtensorMapL2promotion, CUtensorMapFloatOOBfill);

void encode(EncodeFn fn, CUtensorMap* m, void* base, int rank, const cuuint64_t* dims, const cuuint64_t* strides,
            const cuuint32_t* box, CUtensorMapL2promotion promo) {
  cuuint32_t es[5] = {1, 1, 1, 1, 1};
  CUresult res = fn(m, CU_TENSOR_MAP_DATA_TYPE_BFLOAT16, (cuuint32_t)rank, base, dims, strides, box, es, CU_TENSOR_MAP_INTERLEAVE_NONE,
     CU_TENSOR_MAP_SWIZZLE_128B, promo, CU_TENSOR_MAP_FLOAT_OOB_FILL_NONE);
  (void)res;
}

}

extern "C" void kernel_launch(void* const* d_in, const int* in_sizes, int n_in, void* d_out, int out_size) {
  (void)in_sizes; (void)n_in; (void)out_size;
  static EncodeFn fn = nullptr;
  if (!fn) {
    void* p = nullptr;
    cudaDriverEntryPointQueryResult qr;
    cudaGetDriverEntryPoint("cuTensorMapEncodeTiled", &p, cudaEnableDefault, &qr);
    fn = (EncodeFn)p;
    cudaFuncSetAttribute(gqa_fused_kernel, cudaFuncAttributeMaxDynamicSharedMemorySize, SMEM_BYTES);
  }
  void* x = d_in[0];
  void* kc = d_in[1];
  void* vc = d_in[2];
  void* wq = d_in[3];
  char* wo = (char*)d_in[4];
  void* o_scratch = nullptr;
  cudaGetSymbolAddress(&o_scratch, g_o);

  Maps maps;
  const CUtensorMapL2promotion P128 = CU_TENSOR_MAP_L2_PROMOTION_L2_128B, P256 = CU_TENSOR_MAP_L2_PROMOTION_L2_256B;
  {
    cuuint64_t dims[2] = {DM, (cuuint64_t)NBATCH * SQ}, str[1] = {DM * 2};
    cuuint32_t box[2] = {64, 96};
    encode(fn, &maps.x, x, 2, dims, str, box, P128);
  }
  {
    cuuint64_t dims[3] = {64, DM, NH * DH / 64}, str[2] = {NH * DH * 2, 128};
    cuuint32_t box[3] = {64, 64, 2};
    encode(fn, &maps.wq, wq, 3, dims, str, box, P128);
  }
  {
    cuuint64_t dims[3] = {64, (cuuint64_t)NBATCH * NH * SK, 2}, str[2] = {DH * 2, 128};
    cuuint32_t box[3] = {64, 64, 2};
    encode(fn, &maps.k, kc, 3, dims, str, box, P256);
    encode(fn, &maps.v, vc, 3, dims, str, box, P256);
  }
  {
    cuuint64_t dims[2] = {64, (cuuint64_t)NBATCH * NH * 2 * SQ}, str[1] = {128};
    cuuint32_t box[2] = {64, 96};
    encode(fn, &maps.o, o_scratch, 2, dims, str, box, P128);
  }
  for (int c = 0; c < 4; c++) {
    const cuuint64_t rb = DM * 2;
    cuuint64_t dims[5] = {160, 2, 4, 16, NH}, str[4] = {rb, 32 * rb, 2 * rb, 128 * rb};
    cuuint32_t box[5] = {64, 2, 4, 8, 1};
    encode(fn, &maps.wo[c], wo + c * 320, 5, dims, str, box, P128);
  }
  gqa_fused_kernel<<<NCTA, NTHREADS, SMEM_BYTES>>>(maps, (__nv_bfloat16*)d_out);
}
```
